```python
import torch

def _softmax(x, axis=-1):
    return torch.softmax(x, dim=axis)
def _gelu(x):
    return torch.nn.functional.gelu(x, approximate="tanh")
def _silu(x):
    return torch.nn.functional.silu(x)
def _sigmoid(x):
    return torch.sigmoid(x)
def _layernorm(x, axis=-1, eps=1e-5):
    m = x.mean(dim=axis, keepdim=True)
    v = x.var(dim=axis, keepdim=True, unbiased=False)
    return (x - m) / torch.sqrt(v + eps)
def _scatter_add(tgt, idx, src, axis=0):
    return tgt.clone().index_add_(axis, idx, src)
def _segment_sum(src, seg, n):
    out = torch.zeros((n,) + src.shape[1:], dtype=src.dtype)
    return out.index_add_(0, seg, src)
def _pad(x, pw):
    flat = tuple(v for pair in reversed(pw) for v in pair)
    return torch.nn.functional.pad(x, flat)

kernel_name = 'recurrent_scan__sliding_block_cached__dense_activation_squared_relu__decode'

def setup_inputs():

    _w = (lambda a: (lambda t: t.to(torch.bfloat16) if t.is_floating_point() else t)(torch.as_tensor(a)))
    def _A_setup():
        B, Sq, D = 2, 1, 640
        Hq, Hkv, Sk, Dh = 32, 32, 8192, 192
        assert Hq % Hkv == 0, (Hq, Hkv)
        return {
            "x": _w((lambda *s: torch.randn(*s, dtype=torch.bfloat16) * 0.05)(B, Sq, D)),
            "k_cache": _w((lambda *s: torch.randn(*s, dtype=torch.bfloat16) * 0.8)(B, Hkv, Sk, Dh)),
            "v_cache": _w((lambda *s: torch.randn(*s, dtype=torch.bfloat16) * 0.2)(B, Hkv, Sk, Dh)),
            "wq": _w((lambda *s: torch.randn(*s, dtype=torch.bfloat16) * 0.8)(D, Hq * Dh) * (D ** -0.5)),
            "wo": _w((lambda *s: torch.randn(*s, dtype=torch.bfloat16) * 0.2)(Hq * Dh, D) * ((Hq * Dh) ** -0.5)),
        }
    _A_in = _A_setup()

    def _B_setup():
        B, S, D, F = 2, 1, 640, 1536
        return {
            "x": _w((lambda *s: torch.randn(*s, dtype=torch.bfloat16) * 0.05)(B, S, D)),
            "w1": _w((lambda *s: torch.randn(*s, dtype=torch.bfloat16) * 0.1)(D, F)),
            "b1": _w((lambda *s: torch.randn(*s, dtype=torch.bfloat16) * 0.8)(F)),
            "w2": _w((lambda *s: torch.randn(*s, dtype=torch.bfloat16) * 0.1)(F, D)),
            "b2": _w((lambda *s: torch.randn(*s, dtype=torch.bfloat16) * 12.8)(D)),
        }
    _B_in = _B_setup()

    return {
        "A_x": _A_in["x"],
        "A_k_cache": _A_in["k_cache"],
        "A_v_cache": _A_in["v_cache"],
        "A_wq": _A_in["wq"],
        "A_wo": _A_in["wo"],
        "B_x": _B_in["x"],
        "B_w1": _B_in["w1"],
        "B_b1": _B_in["b1"],
        "B_w2": _B_in["w2"],
        "B_b2": _B_in["b2"],
    }

def reference(A_x, A_k_cache, A_v_cache, A_wq, A_wo, B_x, B_w1, B_b1, B_w2, B_b2):
    def _A_ref(x, k_cache, v_cache, wq, wo):
        B, Sq, D = x.shape
        Hq, Dh = 32, 192
        Hkv, Sk = k_cache.shape[1], k_cache.shape[2]
        W = min(4096, max(256, Sk // 4))
        rep = Hq // Hkv
        q = (lambda x, *d: x.permute(*d))((x @ wq).reshape(B, Sq, Hq, Dh), 0, 2, 1, 3)
        k = (lambda x, n, axis: torch.repeat_interleave(x, n, dim=axis))(k_cache[:, :, Sk - W:, :], rep, axis=1)
        v = (lambda x, n, axis: torch.repeat_interleave(x, n, dim=axis))(v_cache[:, :, Sk - W:, :], rep, axis=1)
        scores = torch.einsum("bhqd,bhkd->bhqk", q, k) * (Dh ** -0.5)
        p = _softmax(scores, axis=-1)
        o = torch.einsum("bhqk,bhkd->bhqd", p, v)
        return (lambda x, *d: x.permute(*d))(o, 0, 2, 1, 3).reshape(B, Sq, Hq * Dh) @ wo

    def _B_ref(x, w1, b1, w2, b2):
        h = torch.einsum("bsd,df->bsf", x, w1) + b1
        zero = torch.zeros_like(h)
        r = torch.where(h > zero, h, zero)
        h = r * r
        out = torch.einsum("bsf,fd->bsd", h, w2) + b2
        return out

    x = A_x
    xn = _layernorm(x, axis=-1)
    s = _A_ref(xn, A_k_cache, A_v_cache, A_wq, A_wo)
    g = _silu(_B_ref(xn, B_w1, B_b1, B_w2, B_b2))
    return x + s * g
```

```cpp
#include <cuda_runtime.h>
#include <cuda.h>
#include <cuda_bf16.h>
#include <stdint.h>

#define FORCE_PLAIN 0

namespace {

constexpr int D_ = 640, H_ = 32, DH = 192, SK = 8192, WIN = 2048, F_ = 1536;
constexpr int NATT = 128, NFFN = 4, NCTA = NATT + NFFN;
constexpr int NCONS = 8;
constexpr int NTHREADS = (NCONS + 5) * 32;
constexpr int NOWN = 40;

constexpr int WIN_BASE = 4, WIN_MID = 5, MID_FROM = 18, MID_TO = 58, WIN_FFN = 6;
constexpr int BAL_FROM = 12, BAL_TO = 72, BAL_DN = -64, BAL_UP = 128;

constexpr int TILE = 32 * 384;
constexpr int WOBOX = 16 * 640;
constexpr int NS = 12;
constexpr int OFF_RING = 0;
constexpr int OFF_W = NS * TILE;
constexpr int OFF_SC = OFF_W + 5 * TILE;
constexpr int OFF_WARP = OFF_SC + 6144;
constexpr int WARP_BYTES = 256 + 128;
constexpr int XN_PITCH = 648;
constexpr int OFF_XN = OFF_WARP + 6 * WARP_BYTES;
constexpr int OFF_OF = OFF_XN + 2 * XN_PITCH * 2;
constexpr int OF_PITCH = 104;
constexpr int OFF_PROG = OFF_OF + 416;
constexpr int OFF_TAG = OFF_OF + 432;
constexpr int OFF_RED = OFF_OF + 448;
constexpr int OFF_BAR = OFF_RED + 1024;
constexpr int SMEM_BYTES = OFF_BAR + 96 * 8;
constexpr int OFF_HS = OFF_SC;
constexpr int HS_PITCH = 392;
static_assert(SMEM_BYTES <= 232448, "smem");

constexpr int BAR_WQ = 1  , BAR_FULL = 5  , BAR_WO = 69  , BAR_LATE = 75, BAR_WFREE = 76, BAR_EMPTY = 77  , NBARS = 89;

constexpr int OSLOT = 32;
constexpr int QX_OFF = 0;
constexpr int OX_OFF = QX_OFF + H_ * 2 * DH;
constexpr int SX_OFF = OX_OFF + H_ * 8 * 2 * 16 * OSLOT;
constexpr int FX_OFF = SX_OFF + NOWN * 64 * 32;
constexpr int SCR_WORDS = FX_OFF + NOWN * NFFN * 32;
__device__ __align__(128) uint32_t g_scratch[SCR_WORDS];
__device__ uint32_t g_epoch;
__device__ __align__(128) uint32_t g_prog[64];
#define g_qx (g_scratch + QX_OFF)
#define g_ox (g_scratch + OX_OFF)
#define g_sx (g_scratch + SX_OFF)
#define g_fx (g_scratch + FX_OFF)

constexpr uint32_t SPIN_LIMIT = 1u << 22;

__device__ __forceinline__ void mbar_init(uint32_t a, uint32_t c) { asm volatile("mbarrier.init.shared::cta.b64 [%0], %1;" ::"r"(a), "r"(c) : "memory"); }
__device__ __forceinline__ void mbar_expect_tx(uint32_t a, uint32_t b) { asm volatile("mbarrier.arrive.expect_tx.shared::cta.b64 _, [%0], %1;" ::"r"(a), "r"(b) : "memory"); }
__device__ __forceinline__ void mbar_arrive(uint32_t a) { asm volatile("mbarrier.arrive.shared::cta.b64 _, [%0];" ::"r"(a) : "memory"); }
__device__ __forceinline__ void mbar_wait(uint32_t a, uint32_t ph) {
    uint32_t ok, it = 0;
    do {
        asm volatile("{\n.reg .pred p;\nmbarrier.try_wait.parity.shared::cta.b64 p, [%1], %2;\nselp.u32 %0, 1, 0, p;\n}"
                     : "=r"(ok) : "r"(a), "r"(ph) : "memory");
        if (++it > SPIN_LIMIT) __trap();
    } while (!ok);
}
__device__ __forceinline__ bool mbar_test(uint32_t a) {
    uint32_t ok;
    asm volatile("{\n.reg .pred p;\nmbarrier.test_wait.parity.shared::cta.b64 p, [%1], 0;\nselp.u32 %0, 1, 0, p;\n}" : "=r"(ok) : "r"(a) : "memory");
    return __all_sync(0xffffffffu, ok);
}
__device__ __forceinline__ bool elect_one() {
    uint32_t p;
    asm volatile("{\n.reg .pred P;\nelect.sync _|P, 0xffffffff;\nselp.u32 %0, 1, 0, P;\n}" : "=r"(p));
    return p;
}
constexpr uint64_t POL_EVICT_FIRST = 0x12F0000000000000ull;
__device__ __forceinline__ void bulk_g2s(uint32_t dst, const void* src, uint32_t bytes, uint32_t mbar) {
    asm volatile("cp.async.bulk.shared::cluster.global.mbarrier::complete_tx::bytes.L2::cache_hint [%0], [%1], %2, [%3], %4;"
                 ::"r"(dst), "l"(src), "r"(bytes), "r"(mbar), "l"(POL_EVICT_FIRST) : "memory");
}
__device__ __forceinline__ void tma3d(uint32_t dst, const CUtensorMap* tm, int c0, int c1, int c2, uint32_t mbar) {
    asm volatile("cp.async.bulk.tensor.3d.shared::cluster.global.mbarrier::complete_tx::bytes.L2::cache_hint [%0], [%1, {%2, %3, %4}], [%5], %6;"
                 ::"r"(dst), "l"(tm), "r"(c0), "r"(c1), "r"(c2), "r"(mbar), "l"(POL_EVICT_FIRST) : "memory");
}
__device__ __forceinline__ void prefetch_tm(const CUtensorMap* tm) { asm volatile("prefetch.tensormap [%0];" ::"l"(tm) : "memory"); }
__device__ __forceinline__ uint32_t swz(int line, int c) { return line * 128 + ((c ^ (line & 7)) << 4); }
__device__ __forceinline__ void ldsm4(uint32_t a, uint32_t& r0, uint32_t& r1, uint32_t& r2, uint32_t& r3) {
    asm volatile("ldmatrix.sync.aligned.m8n8.x4.shared.b16 {%0,%1,%2,%3}, [%4];" : "=r"(r0), "=r"(r1), "=r"(r2), "=r"(r3) : "r"(a) : "memory");
}
__device__ __forceinline__ void ldsm4t(uint32_t a, uint32_t& r0, uint32_t& r1, uint32_t& r2, uint32_t& r3) {
    asm volatile("ldmatrix.sync.aligned.m8n8.x4.trans.shared.b16 {%0,%1,%2,%3}, [%4];" : "=r"(r0), "=r"(r1), "=r"(r2), "=r"(r3) : "r"(a) : "memory");
}
__device__ __forceinline__ void mma16816(float (&c)[4], uint32_t a0, uint32_t a1, uint32_t a2, uint32_t a3, uint32_t b0, uint32_t b1) {
    asm volatile("mma.sync.aligned.m16n8k16.row.col.f32.bf16.bf16.f32 {%0,%1,%2,%3}, {%4,%5,%6,%7}, {%8,%9}, {%0,%1,%2,%3};"
                 : "+f"(c[0]), "+f"(c[1]), "+f"(c[2]), "+f"(c[3]) : "r"(a0), "r"(a1), "r"(a2), "r"(a3), "r"(b0), "r"(b1));
}
__device__ __forceinline__ uint32_t lds32(uint32_t a) { uint32_t v; asm volatile("ld.shared.u32 %0, [%1];" : "=r"(v) : "r"(a) : "memory"); return v; }
__device__ __forceinline__ void sts32(uint32_t a, uint32_t v) { asm volatile("st.shared.u32 [%0], %1;" ::"r"(a), "r"(v) : "memory"); }
__device__ __forceinline__ void sts16(uint32_t a, float v) {
    asm volatile("{\n.reg .b16 h;\ncvt.rn.bf16.f32 h, %1;\nst.shared.b16 [%0], h;\n}" ::"r"(a), "f"(v) : "memory");
}
template <typename T> __device__ __forceinline__ void pin(T*& v) { asm volatile("" : "+l"(v)); }
__device__ __forceinline__ void pin(uint32_t& v) { asm volatile("" : "+r"(v)); }
__device__ __forceinline__ void cons_sync() { asm volatile("bar.sync 1, 256;" ::: "memory"); }

__device__ __forceinline__ float bfr(float x) { return __bfloat162float(__float2bfloat16_rn(x)); }
__device__ __forceinline__ uint32_t pack2(float lo, float hi) { __nv_bfloat162 v = __floats2bfloat162_rn(lo, hi); return *reinterpret_cast<uint32_t*>(&v); }
__device__ __forceinline__ float bf_lo(uint32_t u) { return __uint_as_float(u << 16); }
__device__ __forceinline__ float bf_hi(uint32_t u) { return __uint_as_float(u & 0xffff0000u); }
__device__ __forceinline__ float dec(uint32_t u) { return __uint_as_float(u & ~3u); }
__device__ __forceinline__ void put(uint32_t* p, uint32_t u) { asm volatile("st.relaxed.gpu.global.u32 [%0], %1;" ::"l"(p), "r"(u) : "memory"); }
__device__ __forceinline__ void post(uint32_t* p, float x, uint32_t tag) { put(p, (__float_as_uint(x) & ~3u) | tag); }
__device__ __forceinline__ uint2 peek2(const uint32_t* p) {
    uint2 v; asm volatile("ld.relaxed.gpu.global.v2.u32 {%0,%1}, [%2];" : "=r"(v.x), "=r"(v.y) : "l"(p) : "memory"); return v;
}
__device__ __forceinline__ uint4 peek4(const uint32_t* p) {
    uint4 v; asm volatile("ld.relaxed.gpu.global.v4.u32 {%0,%1,%2,%3}, [%4];" : "=r"(v.x), "=r"(v.y), "=r"(v.z), "=r"(v.w) : "l"(p) : "memory"); return v;
}
__device__ __forceinline__ uint32_t bad2(const uint2& v, uint32_t t) { return (v.x ^ t) | (v.y ^ t); }
__device__ __forceinline__ uint32_t bad4(const uint4& v, uint32_t t) { return (v.x ^ t) | (v.y ^ t) | (v.z ^ t) | (v.w ^ t); }
__device__ __forceinline__ bool warp_ok(uint32_t bad) { return __all_sync(0xffffffffu, (bad & 3u) == 0); }
__device__ __forceinline__ void peek(uint2& v, const uint32_t* p) { v = peek2(p); }
__device__ __forceinline__ void peek(uint4& v, const uint32_t* p) { v = peek4(p); }
__device__ __forceinline__ bool fresh(const uint2& v, uint32_t t) { return (bad2(v, t) & 3u) == 0; }
__device__ __forceinline__ bool fresh(const uint4& v, uint32_t t) { return (bad4(v, t) & 3u) == 0; }
template <int STRIDE, typename V, int N>
__device__ __forceinline__ void gather(V (&u)[N], const uint32_t* p, uint32_t tag) {
    uint32_t it = 0;
#pragma unroll
    for (int i = 0; i < N; i++) peek(u[i], p + i * STRIDE);
    while (true) {
        bool ok = true;
#pragma unroll
        for (int i = 0; i < N; i++) ok = ok && fresh(u[i], tag);
        if (__all_sync(0xffffffffu, ok)) break;
#pragma unroll
        for (int i = 0; i < N; i++) if (!fresh(u[i], tag)) peek(u[i], p + i * STRIDE);
        if (++it > SPIN_LIMIT) __trap();
    }
}
__device__ __forceinline__ void peek4_if(uint4& v, const uint32_t* p, uint32_t cond) {
    asm volatile("{\n.reg .pred q;\nsetp.ne.u32 q, %5, 0;\n@q ld.relaxed.gpu.global.v4.u32 {%0,%1,%2,%3}, [%4];\n}"
                 : "+r"(v.x), "+r"(v.y), "+r"(v.z), "+r"(v.w) : "l"(p), "r"(cond) : "memory");
}
__device__ __forceinline__ float pick(const float (&c)[4], int tq) {
    float lo = (tq & 1) ? c[2] : c[0], hi = (tq & 1) ? c[3] : c[1];
    return (tq & 2) ? hi : lo;
}
__device__ __forceinline__ float scatter4(float a0, float a1, float a2, float a3, int lane) {
    const bool hi = lane & 8;
    const float t0 = (hi ? a2 : a0) + __shfl_xor_sync(0xffffffffu, hi ? a0 : a2, 8);
    const float t1 = (hi ? a3 : a1) + __shfl_xor_sync(0xffffffffu, hi ? a1 : a3, 8);
    const bool h2 = lane & 16;
    return (h2 ? t1 : t0) + __shfl_xor_sync(0xffffffffu, h2 ? t0 : t1, 16);
}
__device__ __forceinline__ float silu_bf(float f) { return bfr(__fdividef(f, 1.f + __expf(-f))); }

struct Params {
    const __nv_bfloat16 *x, *k, *v, *b1, *b2;
    __nv_bfloat16* out;
    CUtensorMap wq;
    CUtensorMap wo, w1, w2;
};

__global__ void __launch_bounds__(NTHREADS, 1) fused_decode_kernel(const __grid_constant__ Params P) {
    extern __shared__ __align__(1024) char smem[];
    uint32_t sb;
    asm volatile("mov.u32 %0, %1;" : "=r"(sb) : "r"((uint32_t)__cvta_generic_to_shared(smem)));
    const uint32_t bars = sb + OFF_BAR;
    const int tid = threadIdx.x, lane = tid & 31;
    const int cta = blockIdx.x;
    const bool att = cta < NATT;
    const int mem = cta & 15;
    const size_t kvoff = ((size_t)((cta >> 4) * 4) * SK + (SK - WIN)) * 384 + mem * TILE;

    if (att && tid < 96) asm volatile("prefetch.global.L2 [%0];" ::"l"(reinterpret_cast<const char*>(P.k) + kvoff + tid * 128));
    if (tid == NCONS * 32) {
        mbar_init(bars, 1);
        asm volatile("fence.mbarrier_init.release.cluster;" ::: "memory");
        mbar_expect_tx(bars, TILE);
        if (att) bulk_g2s(sb + OFF_RING, reinterpret_cast<const char*>(P.k) + kvoff, TILE, bars);
#pragma unroll
        for (int i = 1; i < 6; i++) mbar_init(bars + i * 8, 1);
        asm volatile("fence.mbarrier_init.release.cluster;" ::: "memory");
        if (att) {
#pragma unroll
            for (int i = 0; i < 5; i++) {
                mbar_expect_tx(bars + (BAR_WQ + i) * 8, TILE);
                tma3d(sb + OFF_W + i * TILE, &P.wq, 0, cta, i * 128, bars + (BAR_WQ + i) * 8);
            }
        } else {
            tma3d(sb + OFF_RING, &P.w1, 0, mem * 6, 0, bars);
        }
    }
    const int warp = __shfl_sync(0xffffffffu, tid >> 5, 0);
    uint2 xr[5];
    if (warp < 2) {
#pragma unroll
        for (int i = 0; i < 5; i++) xr[i] = __ldg(reinterpret_cast<const uint2*>(P.x + warp * D_) + i * 32 + lane);
    }
    uint32_t epoch = 0;
    if (tid == 96) sts32(sb + OFF_PROG, 0u);
    if (tid == 64 || warp == NCONS) asm volatile("ld.relaxed.gpu.global.u32 %0, [%1];" : "=r"(epoch) : "l"(&g_epoch) : "memory");
    if (lane == 0 && warp != NCONS) {
#pragma unroll 1
        for (int i = 6 + (warp < NCONS ? warp : warp - 1); i < NBARS; i += 12)
            mbar_init(bars + i * 8, i < BAR_LATE ? 1 : i == BAR_LATE ? 2 : att ? 3 : 4);
        asm volatile("fence.mbarrier_init.release.cluster;" ::: "memory");
    }
    __syncthreads();

    const bool owner = att && mem < 5;
    const int own = (cta >> 4) * 5 + mem;
    if (warp == NCONS) {
        if (att) {
            if (elect_one()) prefetch_tm(&P.wo);
            uint32_t slot = 1, ph = 0;
            int done = 0;
            uint32_t* const prog = g_prog + (epoch & 1) * 32;
#pragma unroll 1
            for (int n = 6; n < BAR_WO + 6; n++) {
                const int t = n - 5;
                const char* src = reinterpret_cast<const char*>((t & 4) ? P.v : P.k) + kvoff
                                + (size_t)(((t >> 3) & 1) * H_ + (t >> 4)) * (SK * 384) + (t & 3) * (16 * TILE);
                const uint32_t bar = bars + n * 8;
                if (n >= BAR_WO) { if (n == BAR_WO) mbar_wait(bars + BAR_WFREE * 8, 0); }
                else if (t >= NS) mbar_wait(bars + (BAR_EMPTY + slot) * 8, ph ^ 1);
                if (elect_one()) mbar_expect_tx(bar, n >= BAR_WO ? WOBOX : TILE);
                const int lag = (int)lds32(sb + OFF_PROG) - (n - 7) * NATT;
                const int win = (n >= MID_FROM && n < MID_TO ? WIN_MID : WIN_BASE) + (n < BAL_FROM ? 0 : lag > BAL_UP ? 1 : lag < BAL_DN ? -1 : 0);
                while (n - done >= win) { mbar_wait(bars + done * 8, 0); done++; }
                if (n >= BAR_WO) {
                    const int i = n - BAR_WO;
#pragma unroll
                    for (int hf = 0; hf < 2; hf++) {
                        const int r8b = 2 * i + hf, pos = r8b / 3;
                        if (elect_one())
                            tma3d(sb + OFF_W + r8b * (WOBOX / 2), &P.wo, 0, (cta & 1) * 5,
                                  ((cta >> 4) * 4 + ((pos + 3) & 3)) * DH + (mem >> 1) * 24 + (r8b - 3 * pos) * 8, bar);
                    }
                } else {
                    if (elect_one()) bulk_g2s(sb + OFF_RING + slot * TILE, src, TILE, bar);
                    if (++slot == NS) { slot = 0; ph ^= 1; }
                }
                if ((n & 1) == 0 && n <= BAL_TO && elect_one()) {
                    asm volatile("red.relaxed.gpu.global.add.u32 [%0], 2;" ::"l"(prog) : "memory");
                    asm volatile("cp.async.cg.shared.global [%0], [%1], 16;" ::"r"(sb + OFF_PROG), "l"(prog) : "memory");
                }
            }
            if (cta == 0 && lane == 0) put(g_prog + (~epoch & 1) * 32, 0u);
            asm volatile("cp.async.wait_all;" ::: "memory");
        } else {
            if (elect_one()) prefetch_tm(&P.w2);
            uint32_t slot = 1, ph = 0, wslot = 0, wph = 0;
#pragma unroll 1
            for (int n = 1; n < 88; n++) {
                const uint32_t bar = bars + slot * 8;
                const bool first = n < 40;
                if (n >= NS) mbar_wait(bars + (BAR_EMPTY + slot) * 8, ph ^ 1);
                if (elect_one()) mbar_expect_tx(bar, first ? TILE : WOBOX);
                if (n >= WIN_FFN) { mbar_wait(bars + wslot * 8, wph); if (++wslot == NS) { wslot = 0; wph ^= 1; } }
                if (elect_one())
                    tma3d(sb + OFF_RING + slot * TILE, first ? &P.w1 : &P.w2, 0, first ? mem * 6 + (n & 1) * 3 : (n & 1) * 5,
                          first ? (n >> 1) * 32 : mem * 384 + ((n - 40) >> 1) * 16, bar);
                if (++slot == NS) { slot = 0; ph ^= 1; }
            }
        }
        if (owner) {
            const int word = (lane & 7) * 4 + ((lane >> 2) & 2) + (lane >> 4);
            const int ocol = own * 16 + (word & 15), oidx = (word >> 4) * D_ + ocol;
            const float xv = __bfloat162float(P.x[oidx]);
            const float bv = __bfloat162float(P.b2[ocol]);
            const uint32_t tag = (epoch + 1) & 3u;
            uint4 u[1];
            gather<0>(u, g_fx + own * (NFFN * 32) + lane * 4, tag);
            const float gate = silu_bf(bfr(bfr(scatter4(dec(u[0].x), dec(u[0].y), dec(u[0].z), dec(u[0].w), lane)) + bv));
            __nv_bfloat16* optr = P.out + oidx;
            uint32_t red = sb + OFF_RED + lane * 4;
            pin(optr); pin(red);
#pragma unroll 1
            for (uint32_t pass = 0; pass < 2; pass++) {
                if (pass) asm volatile("bar.sync 4, 288;" ::: "memory");
                float r[8];
#pragma unroll
                for (int w = 0; w < 8; w++) r[w] = __uint_as_float(lds32(red + w * 128));
                const __nv_bfloat16 ov = __float2bfloat16_rn(xv + bfr(bfr(((r[0] + r[1]) + (r[2] + r[3])) + ((r[4] + r[5]) + (r[6] + r[7]))) * gate));
                if (pass) *optr = ov;
            }
            if (own == 0 && lane == 0) put(&g_epoch, epoch + 1);
        }
        return;
    }

    if (warp > NCONS && !att) return;
    const int g = lane >> 2, tq = lane & 3, mi = lane >> 3, r8 = lane & 7;
    const int krow = r8 + 8 * (mi >> 1);
    float bias[3];
    if (!att) {
#pragma unroll
        for (int i = 0; i < 3; i++) bias[i] = __bfloat162float(P.b1[mem * 384 + warp * 48 + i * 16 + (tq & 1) * 8 + g]);
    }
    if (warp < 2) {
        float v[20];
#pragma unroll
        for (int i = 0; i < 5; i++) { v[4 * i] = bf_lo(xr[i].x); v[4 * i + 1] = bf_hi(xr[i].x); v[4 * i + 2] = bf_lo(xr[i].y); v[4 * i + 3] = bf_hi(xr[i].y); }
        float s = 0.f;
#pragma unroll
        for (int i = 0; i < 20; i++) s += v[i];
#pragma unroll
        for (int o = 16; o; o >>= 1) s += __shfl_xor_sync(0xffffffffu, s, o);
        const float mean = s * (1.f / D_);
        float q = 0.f;
#pragma unroll
        for (int i = 0; i < 20; i++) { const float d = v[i] - mean; q += d * d; }
#pragma unroll
        for (int o = 16; o; o >>= 1) q += __shfl_xor_sync(0xffffffffu, q, o);
        const float mb = bfr(mean);
        const float rden = __fdividef(1.f, bfr(sqrtf(bfr(bfr(q * (1.f / D_)) + 1e-5f))));
        uint2* dst = reinterpret_cast<uint2*>(smem + OFF_XN + warp * XN_PITCH * 2);
#pragma unroll
        for (int i = 0; i < 5; i++)
            dst[i * 32 + lane] = make_uint2(pack2(bfr(v[4 * i] - mb) * rden, bfr(v[4 * i + 1] - mb) * rden),
                                            pack2(bfr(v[4 * i + 2] - mb) * rden, bfr(v[4 * i + 3] - mb) * rden));
    }
    if (tid == 64) sts32(sb + OFF_TAG, epoch + 1);
    if (warp < NCONS) cons_sync(); else mbar_wait(bars + BAR_WFREE * 8, 0);
    const uint32_t tag = lds32(sb + OFF_TAG) & 3u;
    uint32_t wooff[5];
    float c[5][4];
    const int mt0 = !att ? (warp & 3) * 5 : warp < 6 ? warp * 2 : warp * 2 - 6;
#pragma unroll
    for (int i = 0; i < 5; i++) {
        const int mt = mt0 + i;
        wooff[i] = sb + swz(5 * krow + (mt >> 2), 2 * (mt & 3) + (mi & 1));
        pin(wooff[i]);
        c[i][0] = c[i][1] = c[i][2] = c[i][3] = 0.f;
    }

    if (att) {
        uint32_t* sdst = g_sx + (((cta & 1) * 20 + mt0) * 64 + (cta >> 1)) * 32 + tq * 8 + g;
        const uint32_t* ssrc = g_sx + (own * 64 + warp * 8) * 32 + lane * 4;
        uint32_t plane = lane, collect = owner && warp < NCONS, redaddr = sb + OFF_RED + tid * 4;
        uint32_t ofaddr = sb + OFF_OF + ((g & 1) * OF_PITCH + 2 * tq) * 2;
        pin(sdst); pin(ssrc); pin(plane); pin(collect); pin(redaddr); pin(ofaddr);
        if (warp >= 5 && warp < NCONS) {
            uint32_t* const qdst = g_qx + ((cta >> 2) * 2 + (tq >> 1)) * DH + (cta & 3) * 48 + (warp - 5) * 16 + (tq & 1) * 8 + g;
            put(qdst, tag ^ 2u);
            float c0[4] = {0.f, 0.f, 0.f, 0.f}, c1[4] = {0.f, 0.f, 0.f, 0.f};
            uint32_t aaddr = sb + OFF_W + krow * 96 + (warp - 5) * 32 + (mi & 1) * 16;
            uint32_t baddr = sb + OFF_XN + ((g & 1) * XN_PITCH + 2 * tq) * 2;
#pragma unroll 1
            for (int i = 0; i < 5; i++) {
                mbar_wait(bars + (BAR_WQ + i) * 8, 0);
#pragma unroll
                for (int u = 0; u < 4; u++) {
                    uint32_t a0, a1, a2, a3;
                    ldsm4t(aaddr + u * 32 * 96, a0, a1, a2, a3);
                    mma16816(c0, a0, a1, a2, a3, lds32(baddr + u * 64), lds32(baddr + u * 64 + 16));
                    ldsm4t(aaddr + (u * 32 + 16) * 96, a0, a1, a2, a3);
                    mma16816(c1, a0, a1, a2, a3, lds32(baddr + u * 64 + 32), lds32(baddr + u * 64 + 48));
                }
                aaddr += TILE; baddr += 256;
            }
            post(qdst, pick(c0, tq) + pick(c1, tq), tag);
            __syncwarp();
            if (lane == 0) mbar_arrive(bars + BAR_WFREE * 8);
        }
        if (warp < 6) {
            const int b = warp >= 3, seg = warp - 3 * b;
            const uint32_t wsm = sb + OFF_WARP + warp * WARP_BYTES;
            uint32_t koff[4], voff[4];
#pragma unroll
            for (int t = 0; t < 4; t++) {
                koff[t] = sb + OFF_RING + seg * 128 + (r8 + 8 * (mi & 1)) * 384 + ((2 * t + (mi >> 1) + r8) & 7) * 16;
                voff[t] = sb + OFF_RING + seg * 128 + krow * 384 + ((2 * t + (mi & 1) + r8) & 7) * 16;
            }
            const int myt = ((g >> 1) - tq) & 3;
            const uint32_t hmask = (g & 1) ? 0xffff0000u : 0x0000ffffu;
            const int d8 = seg * 8 + 2 * tq;
            uint32_t* ox = g_ox + ((cta >> 4) * 4 * 16 + b) * 16 * OSLOT + mem * OSLOT;
            const uint32_t* qsrc = g_qx + ((cta >> 4) * 8 + b) * DH + seg * 64 + 2 * lane;
            uint32_t slot = b * 8, fbar = bars + (BAR_FULL + b * 8) * 8;
            mbar_wait(bars + (b ? BAR_FULL + 4 : BAR_WQ + 4) * 8, 0);
#pragma unroll 1
            for (int hh = 0; hh < 4; hh++) {
                uint32_t* odst0 = ox + (d8 / 3) * (2 * 16 * OSLOT) + (d8 % 3) * 8 + g;
                uint32_t* odst1 = ox + ((d8 + 1) / 3) * (2 * 16 * OSLOT) + ((d8 + 1) % 3) * 8 + g;
                pin(odst0); pin(odst1);
                uint32_t* const stdst = ox + ((seg & 1) * 4 + mi) * (2 * 16 * OSLOT) + 24 + r8;
                uint32_t qf[8];
                {
                    uint2 u; uint32_t it = 0;
                    do { u = peek2(qsrc); if (++it > SPIN_LIMIT) __trap(); } while (!warp_ok(bad2(u, tag)));
                    sts32(wsm + 256 + lane * 4, pack2(dec(u.x), dec(u.y)));
                    __syncwarp();
#pragma unroll
                    for (int cc = 0; cc < 8; cc++) qf[cc] = lds32(wsm + 256 + (((cc + g) & 7) * 8 + 2 * tq) * 2);
                }
                if (hh + b == 4) {
                    put(odst0, tag ^ 2u); put(odst1, tag ^ 2u);
                    if (seg < 2) put(stdst, tag ^ 2u);
                }
                if (hh == 1) { put(sdst, tag ^ 2u); put(sdst + 64 * 32, tag ^ 2u); }
                const uint32_t scb = sb + OFF_SC + (b * 2 + (hh & 1)) * 1536;
#pragma unroll 1
                for (int it = 0; it < 4; it++) {
                    mbar_wait(hh + b + it == 0 ? bars : fbar, 0);
                    const uint32_t base = slot * TILE;
                    float acc[4][4];
#pragma unroll
                    for (int i = 0; i < 4; i++) { acc[i][0] = acc[i][1] = acc[i][2] = acc[i][3] = 0.f; }
#pragma unroll
                    for (int t = 0; t < 4; t++)
#pragma unroll
                        for (int kg = 0; kg < 2; kg++) {
                            uint32_t a0, a1, a2, a3;
                            ldsm4(base + koff[t] + kg * 16 * 384, a0, a1, a2, a3);
                            mma16816(acc[kg * 2 + (t & 1)], a0, a1, a2, a3, qf[2 * t], qf[2 * t + 1]);
                        }
                    __syncwarp();
                    if (lane == 0) mbar_arrive(bars + (BAR_EMPTY + slot) * 8);
                    if (tq == (g >> 1)) {
#pragma unroll
                        for (int kg = 0; kg < 2; kg++) {
                            const float lo = (g & 1) ? acc[kg * 2][1] + acc[kg * 2 + 1][1] : acc[kg * 2][0] + acc[kg * 2 + 1][0];
                            const float hi = (g & 1) ? acc[kg * 2][3] + acc[kg * 2 + 1][3] : acc[kg * 2][2] + acc[kg * 2 + 1][2];
                            sts32(scb + (seg * 128 + it * 32 + kg * 16 + g) * 4, __float_as_uint(lo));
                            sts32(scb + (seg * 128 + it * 32 + kg * 16 + 8 + g) * 4, __float_as_uint(hi));
                        }
                    }
                    if (++slot == NS) slot = 0;
                    fbar += 8;
                }
                asm volatile("bar.sync %0, 96;" ::"r"(2 + b) : "memory");
                {
                    const float4* sp = reinterpret_cast<const float4*>(smem + OFF_SC + (b * 2 + (hh & 1)) * 1536) + lane;
                    const float4 s0 = sp[0], s1 = sp[32], s2 = sp[64];
                    const float x0 = bfr(bfr(s0.x + s1.x + s2.x) * 0.07216878364870323f), x1 = bfr(bfr(s0.y + s1.y + s2.y) * 0.07216878364870323f);
                    const float x2 = bfr(bfr(s0.z + s1.z + s2.z) * 0.07216878364870323f), x3 = bfr(bfr(s0.w + s1.w + s2.w) * 0.07216878364870323f);
                    float m = fmaxf(fmaxf(fmaxf(x0, x1), fmaxf(x2, x3)), -3.3895e38f);
#pragma unroll
                    for (int o = 16; o; o >>= 1) m = fmaxf(m, __shfl_xor_sync(0xffffffffu, m, o));
                    const float e0 = __expf(x0 - m), e1 = __expf(x1 - m), e2 = __expf(x2 - m), e3 = __expf(x3 - m);
                    *reinterpret_cast<uint2*>(smem + OFF_WARP + warp * WARP_BYTES + lane * 8) = make_uint2(pack2(e0, e1), pack2(e2, e3));
                    float l = (e0 + e1) + (e2 + e3);
#pragma unroll
                    for (int o = 16; o; o >>= 1) l += __shfl_xor_sync(0xffffffffu, l, o);
                    if (seg < 2) post(stdst, (r8 & 1) ? l : m, tag);
                    __syncwarp();
                }
                float acc[4][4];
#pragma unroll
                for (int i = 0; i < 4; i++) { acc[i][0] = acc[i][1] = acc[i][2] = acc[i][3] = 0.f; }
#pragma unroll 1
                for (int it = 0; it < 4; it++) {
                    const uint32_t paddr = wsm + (it * 32 + 2 * tq) * 2;
                    uint32_t pl[2], pu[2];
#pragma unroll
                    for (int kg = 0; kg < 2; kg++) { pl[kg] = lds32(paddr + kg * 32) & hmask; pu[kg] = lds32(paddr + kg * 32 + 16) & hmask; }
                    mbar_wait(fbar, 0);
                    const uint32_t base = slot * TILE;
#pragma unroll
                    for (int t = 0; t < 4; t++)
#pragma unroll
                        for (int kg = 0; kg < 2; kg++) {
                            uint32_t a0, a1, a2, a3;
                            ldsm4t(base + voff[t] + kg * 16 * 384, a0, a1, a2, a3);
                            mma16816(acc[kg * 2 + (t & 1)], a0, a1, a2, a3, (t == myt) ? pl[kg] : 0u, (t == myt) ? pu[kg] : 0u);
                        }
                    __syncwarp();
                    if (lane == 0) mbar_arrive(bars + (BAR_EMPTY + slot) * 8);
                    if (++slot == NS) slot = 0;
                    fbar += 8;
                }
                const float c3 = (acc[0][3] + acc[1][3]) + (acc[2][3] + acc[3][3]);
                const float o1 = ((acc[0][1] + acc[1][1]) + (acc[2][1] + acc[3][1])) + ((acc[0][2] + acc[1][2]) + (acc[2][2] + acc[3][2]));
                const float o0 = (acc[0][0] + acc[1][0]) + (acc[2][0] + acc[3][0]) + __shfl_sync(0xffffffffu, c3, (lane & 28) | ((tq - 1) & 3));
                post(odst1, o1, tag);
                post(odst0, o0, tag);
                slot += 8; if (slot >= NS) slot -= NS;
                fbar += 64; ox += 8 * 2 * 16 * OSLOT; qsrc += 2 * DH;
            }
        } else if (warp > NCONS) {
            mbar_wait(bars + (BAR_FULL + 16) * 8, 0);
            put(sdst, tag ^ 2u); put(sdst + 64 * 32, tag ^ 2u);
        } else {
            const int b = warp - 6, sh = lane >= 12, rp = min(lane - 12 * sh, 11);
            const uint32_t* src = g_ox + (((cta >> 4) * 4 * 8 + (mem >> 1)) * 2 + b) * 16 * OSLOT;
            uint32_t tbar = bars + (BAR_FULL + b * 8) * 8;
#pragma unroll 1
            for (int hh = 0; hh < 4; hh++) {
                mbar_wait(tbar + (hh + b == 4 ? 3 : 13) * 8, 0);
                float f[8];
                {
                    uint2 st[1];
                    gather<0>(st, src + (lane & 15) * OSLOT + 24, tag);
                    float mm = dec(st[0].x);
#pragma unroll
                    for (int o = 1; o < 16; o <<= 1) mm = fmaxf(mm, __shfl_xor_sync(0xffffffffu, mm, o));
                    const float e = __expf(dec(st[0].x) - mm);
                    float l = e * dec(st[0].y);
#pragma unroll
                    for (int o = 1; o < 16; o <<= 1) l += __shfl_xor_sync(0xffffffffu, l, o);
                    const float fl = __fdividef(e, l);
#pragma unroll
                    for (int i = 0; i < 8; i++) f[i] = __shfl_sync(0xffffffffu, fl, sh * 8 + i);
                }
                mbar_wait(tbar + 7 * 8, 0);
                uint2 v[8];
                gather<OSLOT>(v, src + sh * 8 * OSLOT + 2 * rp, tag);
                float o[2][2] = {{0.f, 0.f}, {0.f, 0.f}};
#pragma unroll
                for (int i = 0; i < 8; i++) { o[i & 1][0] += f[i] * dec(v[i].x); o[i & 1][1] += f[i] * dec(v[i].y); }
                const float o0 = o[0][0] + o[1][0], o1 = o[0][1] + o[1][1];
                const float p0 = __shfl_down_sync(0xffffffffu, o0, 12), p1 = __shfl_down_sync(0xffffffffu, o1, 12);
                if (lane < 12) sts32(sb + OFF_OF + b * OF_PITCH * 2 + ((hh + 1) & 3) * 48 + lane * 4, pack2(o0 + p0, o1 + p1));
                if (hh == 2) asm volatile("bar.arrive 5, 384;" ::: "memory");
                src += 8 * 2 * 16 * OSLOT; tbar += 16 * 8;
            }
            __syncwarp();
            if (lane == 0) mbar_arrive(bars + BAR_LATE * 8);
        }
#pragma unroll 1
        for (uint32_t pass = 0; pass < 2; pass++) {
            if (warp < 6 || warp > NCONS) {
                float cl[2][4];
#pragma unroll
                for (int i = 0; i < 2; i++) { c[i][0] = c[i][1] = c[i][2] = c[i][3] = cl[i][0] = cl[i][1] = cl[i][2] = cl[i][3] = 0.f; }
                const uint32_t wbar = pass ? bars + BAR_WO * 8 : bars, wstep = pass * 8;
                uint32_t a[4][4], t[2][4], bf[8];
                if (pass) asm volatile("bar.sync 5, 384;" ::: "memory");
#pragma unroll
                for (int i = 0; i < 8; i++) bf[i] = lds32(ofaddr + 64 + i * 16);
                mbar_wait(wbar, 0);
                mbar_wait(wbar + wstep, 0);
#pragma unroll
                for (int i = 0; i < 4; i++) ldsm4t(OFF_W + (i >> 1) * WOBOX + wooff[i & 1], a[i][0], a[i][1], a[i][2], a[i][3]);
                bool late = true;
#pragma unroll
                for (int ks = 2; ks < 7; ks++) {
                    if (ks == 4 ? mbar_test(wbar + 6 * wstep) : ks == 6 && late) {
                        mbar_wait(wbar + 6 * wstep, 0);
                        const uint32_t b0 = lds32(ofaddr), b1 = lds32(ofaddr + 16), b2 = lds32(ofaddr + 32), b3 = lds32(ofaddr + 48);
#pragma unroll
                        for (int i = 0; i < 4; i++) mma16816(cl[i & 1], a[i][0], a[i][1], a[i][2], a[i][3], i < 2 ? b0 : b2, i < 2 ? b1 : b3);
                        late = false;
                    }
                    if (ks < 6) {
                        mbar_wait(wbar + ks * wstep, 0);
#pragma unroll
                        for (int i = 0; i < 2; i++) ldsm4t(OFF_W + ks * WOBOX + wooff[i], t[i][0], t[i][1], t[i][2], t[i][3]);
#pragma unroll
                        for (int i = 0; i < 2; i++) mma16816(c[i], t[i][0], t[i][1], t[i][2], t[i][3], bf[2 * ks - 4], bf[2 * ks - 3]);
                    }
                }
#pragma unroll
                for (int i = 0; i < 2; i++) {
                    const float sv = pick(c[i], plane) + pick(cl[i], plane);
                    if (pass) post(sdst + i * 64 * 32, sv, tag);
                }
            } else if (pass) {
                mbar_wait(bars + (BAR_WO + 5) * 8, 0);
            }
            if (collect) {
                uint4 u0 = make_uint4(tag, tag, tag, tag), u1 = u0;
                uint32_t n0 = pass, n1 = pass, it = 0;
                do {
                    peek4_if(u0, ssrc, n0); peek4_if(u1, ssrc + 128, n1);
                    n0 = bad4(u0, tag) & 3u; n1 = bad4(u1, tag) & 3u;
                    if (++it > SPIN_LIMIT) __trap();
                } while (!__all_sync(0xffffffffu, (n0 | n1) == 0));
                const float s = scatter4(dec(u0.x) + dec(u1.x), dec(u0.y) + dec(u1.y), dec(u0.z) + dec(u1.z), dec(u0.w) + dec(u1.w), plane);
                sts32(redaddr, __float_as_uint(s));
                if (pass) asm volatile("bar.arrive 4, 288;" ::: "memory");
            }
        }
    } else {
        uint32_t slot = warp >> 2, ph = 0;
        {
            float hc[3][4];
            uint32_t aoff[3];
#pragma unroll
            for (int i = 0; i < 3; i++) {
                hc[i][0] = hc[i][1] = hc[i][2] = hc[i][3] = 0.f;
                const int mt = (warp & 3) * 3 + i;
                aoff[i] = sb + OFF_RING + swz(3 * krow + (mt >> 2), 2 * (mt & 3) + (mi & 1));
            }
            uint32_t baddr = sb + OFF_XN + ((g & 1) * XN_PITCH + 2 * tq) * 2;
#pragma unroll 1
            for (int t = 0; t < 20; t++) {
                mbar_wait(bars + slot * 8, ph);
#pragma unroll
                for (int u = 0; u < 2; u++) {
                    const uint32_t b0 = lds32(baddr + u * 32), b1 = lds32(baddr + u * 32 + 16);
#pragma unroll
                    for (int i = 0; i < 3; i++) {
                        uint32_t a0, a1, a2, a3;
                        ldsm4t(slot * TILE + u * 16 * 384 + aoff[i], a0, a1, a2, a3);
                        mma16816(hc[i], a0, a1, a2, a3, b0, b1);
                    }
                }
                __syncwarp();
                if (lane == 0) mbar_arrive(bars + (BAR_EMPTY + slot) * 8);
                baddr += 64;
                slot += 2; if (slot >= NS) { slot -= NS; ph ^= 1; }
            }
            const uint32_t hs = sb + OFF_HS + ((tq >> 1) * HS_PITCH + warp * 48 + (tq & 1) * 8 + g) * 2;
#pragma unroll
            for (int i = 0; i < 3; i++) {
                const float hv = bfr(bfr(pick(hc[i], tq)) + bias[i]);
                const float rv = hv > 0.f ? hv : 0.f;
                sts16(hs + i * 32, rv * rv);
            }
        }
        cons_sync();
        uint32_t baddr = sb + OFF_HS + ((g & 1) * HS_PITCH + 2 * tq) * 2;
#pragma unroll 1
        for (int t = 0; t < 24; t++) {
            const uint32_t b0 = lds32(baddr), b1 = lds32(baddr + 16);
            mbar_wait(bars + slot * 8, ph);
#pragma unroll
            for (int i = 0; i < 5; i++) {
                uint32_t a0, a1, a2, a3;
                ldsm4t(OFF_RING + slot * TILE + wooff[i], a0, a1, a2, a3);
                mma16816(c[i], a0, a1, a2, a3, b0, b1);
            }
            __syncwarp();
            if (lane == 0) mbar_arrive(bars + (BAR_EMPTY + slot) * 8);
            baddr += 32;
            slot += 2; if (slot >= NS) { slot -= NS; ph ^= 1; }
        }
        uint32_t* dst = g_fx + (warp * 5 * NFFN + mem) * 32 + tq * 8 + g;
#pragma unroll
        for (int i = 0; i < 5; i++) post(dst + i * NFFN * 32, pick(c[i], tq), tag);
    }
}

__device__ float g_fb[2 * H_ * DH * 2 + 2 * F_];
__global__ void fb_proj(const __nv_bfloat16* x, const __nv_bfloat16* wq, const __nv_bfloat16* w1, const __nv_bfloat16* b1) {
    __shared__ float xn[2 * D_];
    if (threadIdx.x < 64) {
        const int b = threadIdx.x >> 5, lane = threadIdx.x & 31;
        float s = 0.f, q = 0.f;
        for (int i = lane; i < D_; i += 32) s += __bfloat162float(x[b * D_ + i]);
        for (int o = 16; o; o >>= 1) s += __shfl_xor_sync(0xffffffffu, s, o);
        s *= 1.f / D_;
        for (int i = lane; i < D_; i += 32) { const float d = __bfloat162float(x[b * D_ + i]) - s; q += d * d; }
        for (int o = 16; o; o >>= 1) q += __shfl_xor_sync(0xffffffffu, q, o);
        const float den = bfr(sqrtf(bfr(bfr(q * (1.f / D_)) + 1e-5f)));
        for (int i = lane; i < D_; i += 32) xn[b * D_ + i] = bfr(bfr(__bfloat162float(x[b * D_ + i]) - bfr(s)) / den);
    }
    __syncthreads();
    const int c = blockIdx.x * blockDim.x + threadIdx.x;
    const bool isq = c < H_ * DH;
    const __nv_bfloat16* w = isq ? wq + c : w1 + (c - H_ * DH);
    const int pitch = isq ? H_ * DH : F_;
    float a0 = 0.f, a1 = 0.f;
    for (int d = 0; d < D_; d++) { const float wv = __bfloat162float(w[(size_t)d * pitch]); a0 += xn[d] * wv; a1 += xn[D_ + d] * wv; }
    if (isq) { g_fb[c] = bfr(a0); g_fb[H_ * DH + c] = bfr(a1); }
    else {
        const float bb = __bfloat162float(b1[c - H_ * DH]);
        const float h0 = bfr(bfr(a0) + bb), h1 = bfr(bfr(a1) + bb);
        g_fb[4 * H_ * DH + c - H_ * DH] = h0 > 0.f ? bfr(h0 * h0) : 0.f;
        g_fb[4 * H_ * DH + F_ + c - H_ * DH] = h1 > 0.f ? bfr(h1 * h1) : 0.f;
    }
}
__global__ void fb_attn(const __nv_bfloat16* k, const __nv_bfloat16* v) {
    __shared__ float sc[WIN];
    const size_t base = ((size_t)blockIdx.x * SK + SK - WIN) * DH;
    const float* q = g_fb + blockIdx.x * DH;
    for (int t = threadIdx.x; t < WIN; t += blockDim.x) {
        float s = 0.f;
        for (int d = 0; d < DH; d++) s += q[d] * __bfloat162float(k[base + (size_t)t * DH + d]);
        sc[t] = bfr(bfr(s) * 0.07216878364870323f);
    }
    __syncthreads();
    float m = sc[0], l = 0.f, o = 0.f;
    for (int t = 1; t < WIN; t++) m = fmaxf(m, sc[t]);
    for (int t = 0; t < WIN; t++) l += __expf(sc[t] - m);
    for (int t = 0; t < WIN; t++) o += bfr(__expf(sc[t] - m) / l) * __bfloat162float(v[base + (size_t)t * DH + threadIdx.x]);
    g_fb[2 * H_ * DH + blockIdx.x * DH + threadIdx.x] = bfr(o);
}
__global__ void fb_out(const __nv_bfloat16* x, const __nv_bfloat16* wo, const __nv_bfloat16* w2, const __nv_bfloat16* b2, __nv_bfloat16* out) {
    const int c = blockIdx.x * blockDim.x + threadIdx.x, b = blockIdx.y;
    float s = 0.f, f = 0.f;
    for (int d = 0; d < H_ * DH; d++) s += g_fb[(2 + b) * H_ * DH + d] * __bfloat162float(wo[(size_t)d * D_ + c]);
    for (int d = 0; d < F_; d++) f += g_fb[4 * H_ * DH + b * F_ + d] * __bfloat162float(w2[(size_t)d * D_ + c]);
    out[b * D_ + c] = __float2bfloat16_rn(__bfloat162float(x[b * D_ + c]) + bfr(bfr(s) * silu_bf(bfr(bfr(f) + __bfloat162float(b2[c])))));
}

typedef CUresult (*EncodeFn)(CUtensorMap*, CUtensorMapDataType, cuuint32_t, void*, const cuuint64_t*, const cuuint64_t*,
                             const cuuint32_t*, const cuuint32_t*, CUtensorMapInterleave, CUtensorMapSwizzle,
                             CUtensorMapL2promotion, CUtensorMapFloatOOBfill);

void make_map(EncodeFn fn, CUtensorMap* tm, const void* base, int rows, int cols, int w, int box_segs, int box_rows) {
    const cuuint64_t dims[3] = {(cuuint64_t)w, (cuuint64_t)(cols / w), (cuuint64_t)rows};
    const cuuint64_t strides[2] = {(cuuint64_t)w * 2, (cuuint64_t)cols * 2};
    const cuuint32_t box[3] = {(cuuint32_t)w, (cuuint32_t)box_segs, (cuuint32_t)box_rows};
    const cuuint32_t es[3] = {1, 1, 1};
    fn(tm, CU_TENSOR_MAP_DATA_TYPE_BFLOAT16, 3, const_cast<void*>(base), dims, strides, box, es, CU_TENSOR_MAP_INTERLEAVE_NONE,
       w == 64 ? CU_TENSOR_MAP_SWIZZLE_128B : CU_TENSOR_MAP_SWIZZLE_NONE, CU_TENSOR_MAP_L2_PROMOTION_NONE,
       CU_TENSOR_MAP_FLOAT_OOB_FILL_NONE);
}

}

extern "C" void kernel_launch(void* const* d_in, const int* in_sizes, int n_in, void* d_out, int out_size) {
    (void)in_sizes; (void)n_in; (void)out_size;
    typedef const __nv_bfloat16* BF;
    static EncodeFn encode = nullptr;
    static int mode = 0;
    if (!mode) {
        cudaDriverEntryPointQueryResult st;
        void* fn = nullptr;
        int dev = 0, sms = 0, per_sm = 0;
        cudaGetDriverEntryPoint("cuTensorMapEncodeTiled", &fn, cudaEnableDefault, &st);
        encode = (EncodeFn)fn;
        cudaGetDevice(&dev);
        cudaDeviceGetAttribute(&sms, cudaDevAttrMultiProcessorCount, dev);
        cudaFuncSetAttribute(fused_decode_kernel, cudaFuncAttributeMaxDynamicSharedMemorySize, SMEM_BYTES);
        cudaOccupancyMaxActiveBlocksPerMultiprocessor(&per_sm, fused_decode_kernel, NTHREADS, SMEM_BYTES);
        mode = (encode && sms * per_sm >= NCTA && !FORCE_PLAIN) ? 1 : 2;
        (void)cudaGetLastError();
    }
    if (mode == 2) {
        fb_proj<<<(H_ * DH + F_) / 128, 128, 0, cudaStreamPerThread>>>((BF)d_in[0], (BF)d_in[3], (BF)d_in[6], (BF)d_in[7]);
        fb_attn<<<2 * H_, DH, 0, cudaStreamPerThread>>>((BF)d_in[1], (BF)d_in[2]);
        fb_out<<<dim3(D_ / 64, 2), 64, 0, cudaStreamPerThread>>>((BF)d_in[0], (BF)d_in[4], (BF)d_in[8], (BF)d_in[9], (__nv_bfloat16*)d_out);
        return;
    }
    Params P;
    make_map(encode, &P.wq, d_in[3], D_, H_ * DH, 48, 1, 128);
    make_map(encode, &P.wo, d_in[4], H_ * DH, D_, 64, 5, 8);
    make_map(encode, &P.w1, d_in[6], D_, F_, 64, 3, 32);
    make_map(encode, &P.w2, d_in[8], F_, D_, 64, 5, 16);
    P.x = (BF)d_in[0];
    P.k = (BF)d_in[1];
    P.v = (BF)d_in[2];
    P.b1 = (BF)d_in[7];
    P.b2 = (BF)d_in[9];
    P.out = (__nv_bfloat16*)d_out;
    fused_decode_kernel<<<NCTA, NTHREADS, SMEM_BYTES, cudaStreamPerThread>>>(P);
}
```
